```python
import torch

def _softmax(x, axis=-1):
    return torch.softmax(x, dim=axis)
def _gelu(x):
    return torch.nn.functional.gelu(x, approximate="tanh")
def _silu(x):
    return torch.nn.functional.silu(x)
def _sigmoid(x):
    return torch.sigmoid(x)
def _layernorm(x, axis=-1, eps=1e-5):
    m = x.mean(dim=axis, keepdim=True)
    v = x.var(dim=axis, keepdim=True, unbiased=False)
    return (x - m) / torch.sqrt(v + eps)
def _scatter_add(tgt, idx, src, axis=0):
    return tgt.clone().index_add_(axis, idx, src)
def _segment_sum(src, seg, n):
    out = torch.zeros((n,) + src.shape[1:], dtype=src.dtype)
    return out.index_add_(0, seg, src)
def _pad(x, pw):
    flat = tuple(v for pair in reversed(pw) for v in pair)
    return torch.nn.functional.pad(x, flat)

kernel_name = 'recurrent_scan__sliding_block_cached__glu_gated_swiglu__decode'

def setup_inputs():

    _w = (lambda a: (lambda t: t.to(torch.bfloat16) if t.is_floating_point() else t)(torch.as_tensor(a)))
    def _A_setup():
        B, Sq, D = 1, 1, 448
        Hq, Hkv, Sk, Dh = 16, 8, 65536, 256
        assert Hq % Hkv == 0, (Hq, Hkv)
        return {
            "x": _w((lambda *s: torch.randn(*s, dtype=torch.bfloat16) * 0.05)(B, Sq, D)),
            "k_cache": _w((lambda *s: torch.randn(*s, dtype=torch.bfloat16) * 3.2)(B, Hkv, Sk, Dh)),
            "v_cache": _w((lambda *s: torch.randn(*s, dtype=torch.bfloat16) * 3.2)(B, Hkv, Sk, Dh)),
            "wq": _w((lambda *s: torch.randn(*s, dtype=torch.bfloat16) * 3.2)(D, Hq * Dh) * (D ** -0.5)),
            "wo": _w((lambda *s: torch.randn(*s, dtype=torch.bfloat16) * 3.2)(Hq * Dh, D) * ((Hq * Dh) ** -0.5)),
        }
    _A_in = _A_setup()

    def _B_setup():
        B, S, D, F = 1, 1, 448, 1792
        return {
            "x": _w((lambda *s: torch.randn(*s, dtype=torch.bfloat16) * 0.05)(B, S, D)),
            "w1": _w((lambda *s: torch.randn(*s, dtype=torch.bfloat16) * 0.4)(D, F) * (2.0 / D) ** 0.5),
            "w3": _w((lambda *s: torch.randn(*s, dtype=torch.bfloat16) * 0.4)(D, F) * (2.0 / D) ** 0.5),
            "w2": _w((lambda *s: torch.randn(*s, dtype=torch.bfloat16) * 0.4)(F, D) * (2.0 / F) ** 0.5),
        }
    _B_in = _B_setup()

    return {
        "A_x": _A_in["x"],
        "A_k_cache": _A_in["k_cache"],
        "A_v_cache": _A_in["v_cache"],
        "A_wq": _A_in["wq"],
        "A_wo": _A_in["wo"],
        "B_x": _B_in["x"],
        "B_w1": _B_in["w1"],
        "B_w3": _B_in["w3"],
        "B_w2": _B_in["w2"],
    }

def reference(A_x, A_k_cache, A_v_cache, A_wq, A_wo, B_x, B_w1, B_w3, B_w2):
    def _A_ref(x, k_cache, v_cache, wq, wo):
        B, Sq, D = x.shape
        Hq, Dh = 16, 256
        Hkv, Sk = k_cache.shape[1], k_cache.shape[2]
        W = min(4096, max(256, Sk // 4))
        rep = Hq // Hkv
        q = (lambda x, *d: x.permute(*d))((x @ wq).reshape(B, Sq, Hq, Dh), 0, 2, 1, 3)
        k = (lambda x, n, axis: torch.repeat_interleave(x, n, dim=axis))(k_cache[:, :, Sk - W:, :], rep, axis=1)
        v = (lambda x, n, axis: torch.repeat_interleave(x, n, dim=axis))(v_cache[:, :, Sk - W:, :], rep, axis=1)
        scores = torch.einsum("bhqd,bhkd->bhqk", q, k) * (Dh ** -0.5)
        p = _softmax(scores, axis=-1)
        o = torch.einsum("bhqk,bhkd->bhqd", p, v)
        return (lambda x, *d: x.permute(*d))(o, 0, 2, 1, 3).reshape(B, Sq, Hq * Dh) @ wo

    def _B_ref(x, w1, w3, w2):
        gate = torch.einsum("bsd,df->bsf", x, w1)
        up = torch.einsum("bsd,df->bsf", x, w3)
        h = _silu(gate) * up
        out = torch.einsum("bsf,fd->bsd", h, w2)
        return out

    x = A_x
    xn = _layernorm(x, axis=-1)
    s = _A_ref(xn, A_k_cache, A_v_cache, A_wq, A_wo)
    g = _silu(_B_ref(xn, B_w1, B_w3, B_w2))
    return x + s * g
```

```cpp
#include <cuda_runtime.h>
#include <cuda_bf16.h>
#include <cuda.h>
#include <stdint.h>

#define PER16 660
#define TOFF 800
#define QWARM 0
#define FWAIT 3
#define GDELAY 0
#define TG 1700
#define QDELAY 2000
#define GATE 0
#define PREW 1
#define ATOM_GATE 1

namespace {

constexpr int D = 448, SK = 65536, WIN = 4096, FF = 1792;
constexpr int NCTA = 128;
constexpr int NTHREADS = 704;

constexpr uint32_t SM_WQ = 0;
constexpr uint32_t SM_K = 28672;
constexpr uint32_t SM_W1 = SM_K + 4 * 16384;
constexpr uint32_t SM_W2 = SM_K + 6 * 16384;
constexpr uint32_t SM_WO = SM_K + 7 * 16384;
constexpr uint32_t SM_MISC = SM_K + 12 * 16384;
constexpr uint32_t SM_BAR = SM_MISC;
constexpr uint32_t SM_XN = SM_BAR + 256;
constexpr uint32_t SM_Q = SM_XN + 1024;
constexpr uint32_t SM_P = SM_Q + 1056;
constexpr uint32_t SM_O = SM_P + 1056;
constexpr uint32_t SM_H = SM_O + 512;
constexpr uint32_t SM_WM = SM_H + 256;
constexpr uint32_t SM_WL = SM_WM + 64;
constexpr uint32_t SM_GF = SM_WL + 64;
constexpr uint32_t SM_TAG = SM_GF + 64;
constexpr uint32_t SM_TOTAL = SM_TAG + 16;
static_assert(SM_TOTAL <= 232448, "smem");

constexpr int B_WQ = 0, B_K = 2, B_V = 10, B_W1 = 18, B_W2 = 20, B_WO = 21;

struct Scratch {
    float q[2][4096];
    float g[112][8][16];
    float ml[8][16][8];
    float o[16][16][16][16];
    float bp[56][16][8];
    float sp[56][16][8];
    uint32_t epoch;
    uint32_t pad[31];
};
__device__ Scratch g_scratch;

struct Params {
    const __nv_bfloat16* x;
    Scratch* sc;
    __nv_bfloat16* out;
};
struct Maps {
    CUtensorMap wq, k, v, w1, w3, w2, wo;
};

__device__ __forceinline__ void mbar_init(uint32_t a) {
    asm volatile("mbarrier.init.shared.b64 [%0], 1;" ::"r"(a) : "memory");
}
__device__ __forceinline__ void mbar_expect(uint32_t a, uint32_t b) {
    asm volatile("mbarrier.arrive.expect_tx.shared.b64 _, [%0], %1;" ::"r"(a), "r"(b) : "memory");
}
__device__ __forceinline__ void mbar_wait(uint32_t a) {
    asm volatile(
        "{\n.reg .pred p;\n.reg .u32 n;\nmov.u32 n, 0;\n"
        "W: mbarrier.try_wait.parity.shared.b64 p, [%0], 0;\n"
        "@p bra D;\nadd.u32 n, n, 1;\nsetp.lt.u32 p, n, 4000000;\n@p bra W;\ntrap;\nD:\n}" ::"r"(a)
        : "memory");
}
__device__ __forceinline__ uint64_t evict_first() {
    uint64_t pol;
    asm("createpolicy.fractional.L2::evict_first.b64 %0, 1.0;" : "=l"(pol));
    return pol;
}
__device__ __forceinline__ void tma2d(uint32_t dst, const CUtensorMap* tm, int c0, int c1, uint32_t mbar) {
    asm volatile(
        "cp.async.bulk.tensor.2d.shared::cluster.global.mbarrier::complete_tx::bytes.L2::cache_hint [%0], [%1, {%3, %4}], [%2], %5;" ::"r"(dst),
        "l"(tm), "r"(mbar), "r"(c0), "r"(c1), "l"(evict_first())
        : "memory");
}
__device__ __forceinline__ void tma3d(uint32_t dst, const CUtensorMap* tm, int c1, uint32_t mbar) {
    asm volatile(
        "cp.async.bulk.tensor.3d.shared::cluster.global.mbarrier::complete_tx::bytes.L2::cache_hint [%0], [%1, {%4, %3, %4}], [%2], %5;" ::"r"(dst),
        "l"(tm), "r"(mbar), "r"(c1), "r"(0), "l"(evict_first())
        : "memory");
}
__device__ __forceinline__ bool elect() {
    uint32_t p;
    asm volatile("{ .reg .pred P; elect.sync _|P, 0xffffffff; selp.u32 %0, 1, 0, P; }" : "=r"(p));
    return p;
}
template <int ID, int N>
__device__ __forceinline__ void bar_sync() {
    asm volatile("bar.sync %0, %1;" ::"n"(ID), "n"(N) : "memory");
}
template <int ID, int N>
__device__ __forceinline__ void bar_arrive() {
    asm volatile("bar.arrive %0, %1;" ::"n"(ID), "n"(N) : "memory");
}
__device__ __forceinline__ float4 lds128f(uint32_t a) {
    float4 v;
    asm volatile("ld.shared.v4.f32 {%0,%1,%2,%3}, [%4];" : "=f"(v.x), "=f"(v.y), "=f"(v.z), "=f"(v.w) : "r"(a));
    return v;
}
__device__ __forceinline__ float lds32f(uint32_t a) {
    float v;
    asm volatile("ld.shared.f32 %0, [%1];" : "=f"(v) : "r"(a));
    return v;
}
__device__ __forceinline__ void sts32f(uint32_t a, float v) {
    asm volatile("st.shared.f32 [%0], %1;" ::"r"(a), "f"(v) : "memory");
}
__device__ __forceinline__ void sts32(uint32_t a, uint32_t v) {
    asm volatile("st.shared.u32 [%0], %1;" ::"r"(a), "r"(v) : "memory");
}
__device__ __forceinline__ void sts64(uint32_t a, uint32_t x, uint32_t y) {
    asm volatile("st.shared.v2.u32 [%0], {%1,%2};" ::"r"(a), "r"(x), "r"(y) : "memory");
}
__device__ __forceinline__ void sts_bf16(uint32_t a, float v) {
    asm volatile("st.shared.b16 [%0], %1;" ::"r"(a), "h"(__bfloat16_as_ushort(__float2bfloat16_rn(v))) : "memory");
}
__device__ __forceinline__ void ldsm4(uint32_t a, uint32_t* r) {
    asm volatile("ldmatrix.sync.aligned.m8n8.x4.shared.b16 {%0,%1,%2,%3}, [%4];"
                 : "=r"(r[0]), "=r"(r[1]), "=r"(r[2]), "=r"(r[3])
                 : "r"(a));
}
__device__ __forceinline__ void ldsm4t(uint32_t a, uint32_t* r) {
    asm volatile("ldmatrix.sync.aligned.m8n8.x4.trans.shared.b16 {%0,%1,%2,%3}, [%4];"
                 : "=r"(r[0]), "=r"(r[1]), "=r"(r[2]), "=r"(r[3])
                 : "r"(a));
}
__device__ __forceinline__ void mma(float* c, const uint32_t* a, uint32_t b0, uint32_t b1) {
    asm volatile(
        "mma.sync.aligned.m16n8k16.row.col.f32.bf16.bf16.f32 {%0,%1,%2,%3}, {%4,%5,%6,%7}, {%8,%9}, {%0,%1,%2,%3};"
        : "+f"(c[0]), "+f"(c[1]), "+f"(c[2]), "+f"(c[3])
        : "r"(a[0]), "r"(a[1]), "r"(a[2]), "r"(a[3]), "r"(b0), "r"(b1));
}
template <int NS>
__device__ __forceinline__ void gemv_steps(uint32_t addr, const uint32_t* bf, float* c0, float* c1) {
#pragma unroll
    for (int s = 0; s < NS; s++) {
        uint32_t a[4];
        ldsm4t(addr + s * 2048, a);
        mma((s & 1) ? c1 : c0, a, bf[2 * s], bf[2 * s + 1]);
    }
}
__device__ __forceinline__ float bflo(uint32_t u) { return __uint_as_float(u << 16); }
__device__ __forceinline__ float bfhi(uint32_t u) { return __uint_as_float(u & 0xffff0000u); }
__device__ __forceinline__ float bfr(float v) {
    uint32_t u;
    asm("cvt.rn.bf16x2.f32 %0, %1, %2;" : "=r"(u) : "f"(v), "f"(0.f));
    return __uint_as_float(u);
}
template <typename T>
__device__ __forceinline__ void materialize(T*& p) {
    asm volatile("" : "+l"(p));
}
__device__ __forceinline__ uint32_t pack2(float lo, float hi) {
    __nv_bfloat162 t = __floats2bfloat162_rn(lo, hi);
    return *reinterpret_cast<uint32_t*>(&t);
}
__device__ __forceinline__ void put1(float* p, float v, uint32_t tag) {
    uint32_t u = (__float_as_uint(v) & ~1u) | tag;
    asm volatile("st.relaxed.gpu.global.u32 [%0], %1;" ::"l"(p), "r"(u) : "memory");
}
__device__ __forceinline__ void put2(float* p, float a, float b, uint32_t tag) {
    uint32_t u = (__float_as_uint(a) & ~1u) | tag, w = (__float_as_uint(b) & ~1u) | tag;
    asm volatile("st.relaxed.gpu.global.v2.u32 [%0], {%1,%2};" ::"l"(p), "r"(u), "r"(w) : "memory");
}
__device__ __forceinline__ uint4 ldr128(const float* p) {
    uint4 v;
    asm volatile("ld.relaxed.gpu.global.v4.u32 {%0,%1,%2,%3}, [%4];"
                 : "=r"(v.x), "=r"(v.y), "=r"(v.z), "=r"(v.w)
                 : "l"(p)
                 : "memory");
    return v;
}
__device__ __forceinline__ uint2 ldr64(const float* p) {
    uint2 v;
    asm volatile("ld.relaxed.gpu.global.v2.u32 {%0,%1}, [%2];" : "=r"(v.x), "=r"(v.y) : "l"(p) : "memory");
    return v;
}
__device__ __forceinline__ uint32_t ldr32(const float* p) {
    uint32_t v;
    asm volatile("atom.relaxed.gpu.global.or.b32 %0, [%1], 0;" : "=r"(v) : "l"(p) : "memory");
    return v;
}
__device__ __forceinline__ bool bad4(const uint4& v, uint32_t tag) {
    uint32_t t;
    asm("{ .reg .b32 u; lop3.b32 %0, %1, %2, %5, 0x7e; lop3.b32 u, %3, %4, %5, 0x7e; lop3.b32 %0, %0, u, 1, 0xa8; }"
        : "=r"(t) : "r"(v.x), "r"(v.y), "r"(v.z), "r"(v.w), "r"(tag));
    return t;
}
constexpr int SPIN_MAX = 2000000;
template <int N>
__device__ __forceinline__ void poll(uint4* v, const float* p, int stride, uint32_t tag) {
    int it = 0;
    while (true) {
        bool bad[N], any = false;
#pragma unroll
        for (int i = 0; i < N; i++) { bad[i] = bad4(v[i], tag); any |= bad[i]; }
        if (!__any_sync(0xffffffffu, any)) break;
#pragma unroll
        for (int i = 0; i < N; i++)
            if (bad[i]) v[i] = ldr128(p + i * stride);
        if (++it > SPIN_MAX) __trap();
    }
}
__device__ __forceinline__ void spin_cycles(int n) {
    uint32_t c0, c1;
    asm volatile("mov.u32 %0, %clock;" : "=r"(c0)::"memory");
    do { asm volatile("mov.u32 %0, %clock;" : "=r"(c1)::"memory"); } while ((int)(c1 - c0) < n);
}
__device__ __forceinline__ uint32_t now_ns() {
    uint32_t t;
    asm volatile("mov.u32 %0, %globaltimer_lo;" : "=r"(t)::"memory");
    return t;
}
__device__ __forceinline__ float shx(float v, int m) { return __shfl_xor_sync(0xffffffffu, v, m); }
__device__ __forceinline__ float tr(float a, float b, bool upper, int m) {
    float send = upper ? a : b, keep = upper ? b : a;
    return keep + shx(send, m);
}
__device__ __forceinline__ float silu(float v) { return __fdividef(v, 1.f + __expf(-v)); }
__device__ __forceinline__ float uf(uint32_t u) { return __uint_as_float(u); }

#define TS(i)
#define TSW(w_, i)

__global__ void __launch_bounds__(NTHREADS, 1)
fused_kernel(const Params p, const __grid_constant__ Maps tm) {
    extern __shared__ __align__(1024) unsigned char smem[];
    const uint32_t sb = (uint32_t)__cvta_generic_to_shared(smem);
    const int b = blockIdx.x, g = b >> 4, r = b & 15;
    const uint32_t bar = sb + SM_BAR;
    const uint32_t t0 = now_ns();
    if (threadIdx.x == 0) {
        mbar_init(bar + 8 * B_WQ);
        mbar_expect(bar + 8 * B_WQ, 14336);
        tma2d(sb + SM_WQ, &tm.wq, g * 512 + (r >> 1) * 64, (r & 1) * 224, bar + 8 * B_WQ);
        mbar_init(bar + 8 * (B_WQ + 1));
        mbar_expect(bar + 8 * (B_WQ + 1), 14336);
        tma2d(sb + SM_WQ + 14336, &tm.wq, g * 512 + (r >> 1) * 64, (r & 1) * 224 + 112, bar + 8 * (B_WQ + 1));
        asm volatile("prefetch.tensormap [%0];" ::"l"(&tm.k) : "memory");
    }
    const int lane = threadIdx.x & 31;
    const int wid = __shfl_sync(0xffffffffu, threadIdx.x >> 5, 0);
    const bool has_ffn = b < 112;
    const int cb = b % 7, hd = b / 7;

    if (wid == 0) {
        const bool el = elect();
        constexpr uint32_t per16 = PER16, toff = TOFF;
        bar_sync<0, NTHREADS>();
        const int row0 = g * SK + (SK - WIN) + r * 16;
        uint32_t tnext = (t0 + toff) * 16;
#pragma unroll 1
        for (int n = 0; n < 32; n++) {
            const int j = n >> 1;
            if (n == 24) bar_sync<4, 288>();
            if (el && !(n & 1)) mbar_expect(bar + 8 * (B_K + j), 16384);
            while ((int)(now_ns() * 16 - tnext) < 0) {}
            if (el) tma3d(sb + SM_K + (n < 24 ? n : n - 24) * 8192, n < 16 ? &tm.k : &tm.v, row0 + (n & 15) * 256, bar + 8 * (B_K + j));
            tnext += per16 * 8;
            if (n == 8 && el) {
                asm volatile("prefetch.tensormap [%0];" ::"l"(&tm.v) : "memory");
                asm volatile("prefetch.tensormap [%0];" ::"l"(&tm.w1) : "memory");
                asm volatile("prefetch.tensormap [%0];" ::"l"(&tm.w3) : "memory");
                asm volatile("prefetch.tensormap [%0];" ::"l"(&tm.w2) : "memory");
                asm volatile("prefetch.tensormap [%0];" ::"l"(&tm.wo) : "memory");
            }
        }
        TS(6);
        bar_sync<5, 288>();
        if (has_ffn) {
#pragma unroll 1
            for (int n = 0; n < 6; n++) {
                const int m = n >> 1, hf = n & 1;
                if (el && !hf) mbar_expect(bar + 8 * (B_W1 + m), 14336);
                while ((int)(now_ns() * 16 - tnext) < 0) {}
                if (el)
                    tma2d(sb + SM_W1 + m * 16384 + hf * 7168, &tm.w1 + m, m < 2 ? (b >> 2) * 64 : cb * 64,
                          (m < 2 ? (b & 3) : hd) * 112 + hf * 56, bar + 8 * (B_W1 + m));
                tnext += per16 * 49 / 8;
            }
#pragma unroll 1
            for (int c = 0; c < 4; c++) {
                if (el) mbar_expect(bar + 8 * (B_WO + c), 8192);
                while ((int)(now_ns() * 16 - tnext) < 0) {}
                if (el) tma2d(sb + SM_WO + c * 8192, &tm.wo, cb * 64, hd * 256 + c * 64, bar + 8 * (B_WO + c));
                tnext += per16 * 7;
            }
        }
        TS(7);
        return;
    }

    Scratch* sc = p.sc;
    if (wid == 1) {
        uint32_t ep;
        asm volatile("ld.relaxed.gpu.global.u32 %0, [%1];" : "=r"(ep) : "l"(&sc->epoch) : "memory");
        const int fcol = (lane & 1) * 4 + ((lane & 16) ? 2 : 0) + ((lane & 8) ? 1 : 0);
        const int fb = b < 56 ? b : 0;
        const float xres = __bfloat162float(p.x[fb * 8 + fcol]);
        __nv_bfloat16* outp = p.out + fb * 8 + fcol;
        materialize(outp);
        bar_sync<0, NTHREADS>();
        const uint32_t tag = (ep + 1) & 1u;
        if (lane == 0) sts32(sb + SM_TAG, tag);
        __syncwarp();
        bar_arrive<12, 672>();
        bar_sync<7, 288>();
        TS(9);
        {
            float mc = lds32f(sb + SM_WM + (lane & 15) * 4), lc = lds32f(sb + SM_WL + (lane & 15) * 4);
            mc = fmaxf(mc, shx(mc, 2)); mc = fmaxf(mc, shx(mc, 4)); mc = fmaxf(mc, shx(mc, 8));
            lc += shx(lc, 2); lc += shx(lc, 4); lc += shx(lc, 8);
            if (lane < 4) put2(&sc->ml[g][r][lane * 2], mc, lc, tag);
        }
        if (!has_ffn) return;
        {
            mbar_wait(bar + 8 * (B_V + 3));
            uint2 u;
            int it = 0;
            while (true) {
                u = ldr64(&sc->ml[hd >> 1][lane & 15][(hd & 1) * 2]);
                if (!__any_sync(0xffffffffu, ((u.x ^ tag) | (u.y ^ tag)) & 1u)) break;
                if (++it > SPIN_MAX) __trap();
            }
            float mr = uf(u.x & ~1u), lr = uf(u.y);
            float M = mr;
            M = fmaxf(M, shx(M, 1)); M = fmaxf(M, shx(M, 2)); M = fmaxf(M, shx(M, 4)); M = fmaxf(M, shx(M, 8));
            const float e = __expf(mr - M);
            float L = lr * e;
            L += shx(L, 1); L += shx(L, 2); L += shx(L, 4); L += shx(L, 8);
            if (lane < 16) sts32f(sb + SM_GF + lane * 4, __fdividef(e, L));
            TS(10);
            const float* fp = &sc->o[hd][15][lane & 15][0];
            bool bad = lane < 16;
            mbar_wait(bar + 8 * (B_V + 7));
            spin_cycles(GDELAY);
            while (true) {
                if (bad) bad = (ldr32(fp) ^ tag) & 1u;
                if (__popc(__ballot_sync(0xffffffffu, bad)) <= GATE) break;
                if (++it > SPIN_MAX) __trap();
            }
        }
        __syncwarp();
        bar_arrive<13, 288>();
        TS(14);
        if (b < 56) {
            const bool u16 = lane & 16, u8 = lane & 8;
            uint4 v[2];
            mbar_wait(bar + 8 * (B_WO + FWAIT));
            v[0] = ldr128(&sc->bp[b][0][0] + lane * 4); v[1] = ldr128(&sc->sp[b][0][0] + lane * 4);
            poll<2>(v, &sc->bp[b][0][0] + lane * 4, 56 * 128, tag);
            TS(12);
            float t = tr(tr(uf(v[0].x), uf(v[0].z), u16, 16), tr(uf(v[0].y), uf(v[0].w), u16, 16), u8, 8);
            float w = tr(tr(uf(v[1].x), uf(v[1].z), u16, 16), tr(uf(v[1].y), uf(v[1].w), u16, 16), u8, 8);
            t += shx(t, 4); w += shx(w, 4);
            t += shx(t, 2); w += shx(w, 2);
            const float res = xres + bfr(bfr(w) * bfr(silu(bfr(t))));
            if ((lane & 6) == 0)
                asm volatile("st.global.b16 [%0], %1;" ::"l"(outp), "h"(__bfloat16_as_ushort(__float2bfloat16_rn(res))) : "memory");
            if (b == 0 && lane == 0) sc->epoch = ep + 1;
            TS(13);
        }
        return;
    }

    if (wid < 14 && elect()) {
        mbar_init(bar + 8 * (2 * wid - 2));
        mbar_init(bar + 8 * (2 * wid - 1));
    }
    __syncwarp();
    const int li = lane >> 3, l7 = lane & 7, j4 = lane & 3, l4 = lane >> 2;

    if (wid >= 18) {
        const int warp = wid - 18;
        bar_sync<0, NTHREADS>();
        bar_sync<12, 672>();
        if (!has_ffn) return;
        uint32_t tag;
        asm volatile("ld.shared.u32 %0, [%1];" : "=r"(tag) : "r"(sb + SM_TAG));
        const uint32_t aoff = sb + SM_W2 + (l7 + (li >> 1) * 8) * 128 + (((2 * warp + (li & 1)) ^ l7) << 4);
        const float* gp = &sc->g[hd * 7 + 2 * warp][l7][li * 4];
        const int gstride = warp < 3 ? 128 : 0;
        float* bout = &sc->bp[cb * 8 + 2 * warp + (j4 & 1)][hd][l4];
        materialize(bout);
        uint4 gv[2];
        mbar_wait(bar + 8 * B_V);
        if (j4 < 2) put1(bout, 0.f, tag ^ 1u);
        mbar_wait(bar + 8 * (B_V + 7));
        const uint32_t tg = t0 + TOFF + PER16 * 2244 / 128 + TG;
        while ((int)(now_ns() - tg) < 0) {}
        gv[0] = ldr128(gp); gv[1] = ldr128(gp + gstride);
        uint32_t a[7][4], bf[16];
        mbar_wait(bar + 8 * B_W2);
#pragma unroll
        for (int s = 0; s < 7; s++) ldsm4t(aoff + s * 2048, a[s]);
        poll<2>(gv, gp, gstride, tag);
        TSW(0, 28);
        {
            const bool u4 = lane & 4, u2 = lane & 2, u1 = lane & 1;
            float a0 = tr(uf(gv[0].x), uf(gv[1].x), u4, 4), a1 = tr(uf(gv[0].y), uf(gv[1].y), u4, 4);
            float a2 = tr(uf(gv[0].z), uf(gv[1].z), u4, 4), a3 = tr(uf(gv[0].w), uf(gv[1].w), u4, 4);
            float e0 = bfr(tr(a0, a2, u2, 2)), e1 = bfr(tr(a1, a3, u2, 2));
            float o = shx(u1 ? e0 : e1, 1);
            float ga = u1 ? o : e0, up = u1 ? e1 : o;
            sts_bf16(sb + SM_H + ((2 * warp + (u4 ? 1 : 0)) * 16 + li * 4 + j4) * 2, bfr(silu(ga)) * up);
        }
        bar_sync<1, 128>();
#pragma unroll
        for (int i = 0; i < 4; i++) ldsm4(sb + SM_H + i * 64 + li * 16, bf + 4 * i);
        float c[4][4] = {};
#pragma unroll
        for (int s = 0; s < 7; s++) mma(c[s & 3], a[s], bf[2 * s], bf[2 * s + 1]);
        if (j4 < 2)
            put1(bout, j4 ? (c[0][2] + c[1][2]) + (c[2][2] + c[3][2]) : (c[0][0] + c[1][0]) + (c[2][0] + c[3][0]), tag);
        TSW(0, 29);
        return;
    }

    if (wid >= 14) {
        const int warp = wid - 14;
        bar_sync<0, NTHREADS>();
        bar_sync<12, 672>();
        if (!has_ffn) return;
        uint32_t tag;
        asm volatile("ld.shared.u32 %0, [%1];" : "=r"(tag) : "r"(sb + SM_TAG));
        const uint32_t aoff = sb + SM_WO + (l7 + (li >> 1) * 8) * 128 + (((2 * warp + (li & 1)) ^ l7) << 4);
        float* spp = &sc->sp[cb * 8 + 2 * warp + (j4 & 1)][hd][l4];
        materialize(spp);
        mbar_wait(bar + 8 * B_V);
        if (j4 < 2) put1(spp, 0.f, tag ^ 1u);
        uint32_t a[8][4], bf[32];
#pragma unroll
        for (int s = 0; s < 8; s++) {
            if (!(s & 3)) mbar_wait(bar + 8 * (B_WO + (s >> 2)));
            ldsm4t(aoff + s * 2048, a[s]);
        }
        bar_sync<11, 384>();
        TSW(0, 24);
#pragma unroll
        for (int i = 0; i < 8; i++) ldsm4(sb + SM_O + i * 64 + li * 16, bf + 4 * i);
        float c[4][4] = {};
#pragma unroll
        for (int s = 0; s < 8; s++) mma(c[s & 3], a[s], bf[2 * s], bf[2 * s + 1]);
#pragma unroll
        for (int h = 2; h < 4; h++) {
            mbar_wait(bar + 8 * (B_WO + h));
#pragma unroll
            for (int s = 0; s < 4; s++) ldsm4t(aoff + (4 * h + s) * 2048, a[(h & 1) * 4 + s]);
#pragma unroll
            for (int s = 0; s < 4; s++) mma(c[s], a[(h & 1) * 4 + s], bf[8 * h + 2 * s], bf[8 * h + 2 * s + 1]);
        }
        if (j4 < 2)
            put1(spp, j4 ? (c[0][2] + c[1][2]) + (c[2][2] + c[3][2]) : (c[0][0] + c[1][0]) + (c[2][0] + c[3][0]), tag);
        TSW(0, 25);
        return;
    }

    if (wid >= 10) {
        const int warp = wid - 10;
        const uint32_t aoff = (l7 + (li >> 1) * 8) * 128 + (((2 * warp + (li & 1)) ^ l7) << 4);
        bar_sync<0, NTHREADS>();
        bar_sync<12, 672>();
        uint32_t tag;
        asm volatile("ld.shared.u32 %0, [%1];" : "=r"(tag) : "r"(sb + SM_TAG));
        {
            uint32_t bf[28];
#pragma unroll
            for (int i = 0; i < 7; i++) ldsm4(sb + SM_XN + (r & 1) * 448 + i * 64 + li * 16, bf + 4 * i);
            float c0[4] = {0.f, 0.f, 0.f, 0.f}, c1[4] = {0.f, 0.f, 0.f, 0.f};
            mbar_wait(bar + 8 * B_WQ);
            gemv_steps<7>(sb + SM_WQ + aoff, bf, c0, c1);
            mbar_wait(bar + 8 * (B_WQ + 1));
            gemv_steps<7>(sb + SM_WQ + 14336 + aoff, bf + 14, c0, c1);
            if (j4 < 2)
                put1(&sc->q[r & 1][g * 512 + (r >> 1) * 64 + warp * 16 + j4 * 8 + l4], j4 ? c0[2] + c1[2] : c0[0] + c1[0], tag);
            TSW(0, 17);
        }
        if (!has_ffn) return;
        uint32_t bf[16];
#pragma unroll
        for (int i = 0; i < 4; i++) ldsm4(sb + SM_XN + (b & 3) * 224 + i * 64 + li * 16, bf + 4 * i);
        float* gout = &sc->g[(b >> 2) * 4 + warp][(b & 3) * 2][j4 * 8 + l4];
        materialize(gout);
        mbar_wait(bar + 8 * B_V);
        put1(gout, 0.f, tag ^ 1u);
        float c0[4] = {0.f, 0.f, 0.f, 0.f}, c1[4] = {0.f, 0.f, 0.f, 0.f};
        float d0[4] = {0.f, 0.f, 0.f, 0.f}, d1[4] = {0.f, 0.f, 0.f, 0.f};
        mbar_wait(bar + 8 * B_W1);
        gemv_steps<7>(sb + SM_W1 + aoff, bf, c0, c1);
        mbar_wait(bar + 8 * (B_W1 + 1));
        TSW(0, 26);
        gemv_steps<7>(sb + SM_W1 + 16384 + aoff, bf, d0, d1);
        const float lo = (j4 & 2) ? d0[0] + d1[0] : c0[0] + c1[0], hi = (j4 & 2) ? d0[2] + d1[2] : c0[2] + c1[2];
        put1(gout, (j4 & 1) ? hi : lo, tag);
        TSW(0, 27);
        return;
    }

    const int warp = wid - 2, tid = threadIdx.x - 64;
    {
        uint32_t xv[7], xme = 0;
        const uint32_t* xp = reinterpret_cast<const uint32_t*>(p.x);
        if (warp < 7) {
#pragma unroll
            for (int i = 0; i < 7; i++) xv[i] = __ldg(xp + lane + 32 * i);
            xme = __ldg(xp + tid);
        }
        bar_sync<0, NTHREADS>();
        if (warp < 7) {
            float s = 0.f;
#pragma unroll
            for (int i = 0; i < 7; i++) s += bflo(xv[i]) + bfhi(xv[i]);
#pragma unroll
            for (int m = 16; m; m >>= 1) s += shx(s, m);
            const float mean = s * (1.f / D);
            float vs = 0.f;
#pragma unroll
            for (int i = 0; i < 7; i++) {
                float a = bflo(xv[i]) - mean, c = bfhi(xv[i]) - mean;
                vs += a * a + c * c;
            }
#pragma unroll
            for (int m = 16; m; m >>= 1) vs += shx(vs, m);
            const float mb = bfr(mean);
            const float sd = bfr(sqrtf(bfr(bfr(vs * (1.f / D)) + 1e-5f)));
            sts32(sb + SM_XN + tid * 4, pack2(bfr(bflo(xme) - mb) / sd, bfr(bfhi(xme) - mb) / sd));
        }
    }
    bar_sync<12, 672>();
    TSW(0, 16);
    uint32_t tag;
    asm volatile("ld.shared.u32 %0, [%1];" : "=r"(tag) : "r"(sb + SM_TAG));

    if (warp < 4) {
        const float* qp = &sc->q[0][g * 512 + tid * 4];
        uint4 v[2];
        mbar_wait(bar + 8 * (B_WQ + 1));
        spin_cycles(QDELAY);
        v[0] = ldr128(qp); v[1] = ldr128(qp + 4096);
        poll<2>(v, qp, 4096, tag);
        sts64(sb + SM_Q + tid * 8 + (tid >> 6) * 16, pack2(uf(v[0].x) + uf(v[1].x), uf(v[0].y) + uf(v[1].y)),
              pack2(uf(v[0].z) + uf(v[1].z), uf(v[0].w) + uf(v[1].w)));
    }
    bar_sync<3, 256>();
    TSW(0, 18);

    uint32_t bf[32];
    {
#pragma unroll
        for (int i = 0; i < 8; i++) ldsm4(sb + SM_Q + (lane & 1) * 528 + i * 64 + li * 16, bf + 4 * i);
        float s[2][4] = {};
        const uint32_t krow = (l7 + (li & 1) * 8) * 128;
#pragma unroll 1
        for (int h = 0; h < 2; h++) {
            float c0[4] = {0.f, 0.f, 0.f, 0.f}, c1[4] = {0.f, 0.f, 0.f, 0.f};
            mbar_wait(bar + 8 * (B_K + h * 4 + (warp >> 1)));
            const uint32_t base = sb + SM_K + (h * 8 + warp) * 8192 + krow;
#pragma unroll
            for (int ks = 0; ks < 16; ks++) {
                uint32_t a[4];
                ldsm4(base + (ks >> 2) * 2048 + ((((ks & 3) * 2 + (li >> 1)) ^ l7) << 4), a);
                mma((ks & 1) ? c1 : c0, a, bf[2 * ks], bf[2 * ks + 1]);
            }
#pragma unroll
            for (int i = 0; i < 4; i++) {
                s[0][i] = s[1][i];
                s[1][i] = bfr(c0[i] + c1[i]) * 0.0625f;
            }
            if (h == 0) bar_arrive<4, 288>();
        }
        float m0 = fmaxf(fmaxf(s[0][0], s[0][2]), fmaxf(s[1][0], s[1][2]));
        float m1 = fmaxf(fmaxf(s[0][1], s[0][3]), fmaxf(s[1][1], s[1][3]));
#pragma unroll
        for (int m = 4; m < 32; m <<= 1) { m0 = fmaxf(m0, shx(m0, m)); m1 = fmaxf(m1, shx(m1, m)); }
        if (lane < 2) sts32f(sb + SM_WM + (warp * 2 + lane) * 4, lane ? m1 : m0);
        bar_sync<2, 256>();
#pragma unroll
        for (int i = 0; i < 4; i++) {
            float4 w = lds128f(sb + SM_WM + i * 16);
            m0 = fmaxf(m0, fmaxf(w.x, w.z));
            m1 = fmaxf(m1, fmaxf(w.y, w.w));
        }
        const float mm = (j4 & 1) ? m1 : m0;
        const float sa = (j4 & 2) ? ((j4 & 1) ? s[0][3] : s[0][2]) : ((j4 & 1) ? s[0][1] : s[0][0]);
        const float sc2 = (j4 & 2) ? ((j4 & 1) ? s[1][3] : s[1][2]) : ((j4 & 1) ? s[1][1] : s[1][0]);
        const float e0 = __expf(sa - mm), e1 = __expf(sc2 - mm);
        const uint32_t pa = sb + SM_P + (j4 & 1) * 528 + (warp * 16 + (j4 >> 1) * 8 + l4) * 2;
        sts_bf16(pa, e0);
        sts_bf16(pa + 256, e1);
        float l = e0 + e1;
        l += shx(l, 2); l += shx(l, 4); l += shx(l, 8); l += shx(l, 16);
        if (lane < 2) sts32f(sb + SM_WL + (warp * 2 + lane) * 4, l);
        bar_sync<7, 288>();
    }
    TSW(0, 19);

    {
        float* op = &sc->o[2 * g + (j4 & 1)][2 * warp][r][(j4 >> 1) * 8 + l4];
        materialize(op);
        put1(op, 0.f, tag ^ 1u);
        put1(op + 256, 0.f, tag ^ 1u);
        float c0[4] = {0.f, 0.f, 0.f, 0.f}, c1[4] = {0.f, 0.f, 0.f, 0.f};
        const uint32_t vrow = sb + SM_K + (warp >> 1) * 2048 + (l7 + (li >> 1) * 8) * 128;
        const uint32_t ch0 = (((warp & 1) * 4 + (li & 1)) ^ l7) << 4, ch1 = ch0 ^ 32;
#pragma unroll 1
        for (int c = 0; c < 8; c++) {
            uint32_t pf[4];
            ldsm4(sb + SM_P + (lane & 1) * 528 + c * 64 + li * 16, pf);
            mbar_wait(bar + 8 * (B_V + c));
            TSW(1, 40 + c);
            const uint32_t base = vrow + (c < 4 ? c + 8 : c - 4) * 16384;
#pragma unroll
            for (int u = 0; u < 2; u++) {
                uint32_t a0[4], a1[4];
                ldsm4t(base + u * 8192 + ch0, a0);
                ldsm4t(base + u * 8192 + ch1, a1);
                mma(c0, a0, pf[2 * u], pf[2 * u + 1]);
                mma(c1, a1, pf[2 * u], pf[2 * u + 1]);
            }
            if (c == 0) bar_arrive<5, 288>();
        }
        put1(op, (j4 & 2) ? ((j4 & 1) ? c0[3] : c0[2]) : ((j4 & 1) ? c0[1] : c0[0]), tag);
        put1(op + 256, (j4 & 2) ? ((j4 & 1) ? c1[3] : c1[2]) : ((j4 & 1) ? c1[1] : c1[0]), tag);
    }
    TSW(0, 21);
    if (!has_ffn) return;

    {
        const float* opp = &sc->o[hd][2 * warp][l7][li * 4];
        bar_sync<13, 288>();
        uint4 v[4];
#pragma unroll
        for (int i = 0; i < 4; i++) v[i] = ldr128(opp + i * 128);
        const float f0 = lds32f(sb + SM_GF + l7 * 4), f1 = lds32f(sb + SM_GF + 32 + l7 * 4);
        poll<4>(v, opp, 128, tag);
        TSW(0, 23);
        const bool u4 = lane & 4, u2 = lane & 2, u1 = lane & 1;
        float a0 = tr(fmaf(uf(v[0].x), f0, uf(v[1].x) * f1), fmaf(uf(v[2].x), f0, uf(v[3].x) * f1), u4, 4);
        float a1 = tr(fmaf(uf(v[0].y), f0, uf(v[1].y) * f1), fmaf(uf(v[2].y), f0, uf(v[3].y) * f1), u4, 4);
        float a2 = tr(fmaf(uf(v[0].z), f0, uf(v[1].z) * f1), fmaf(uf(v[2].z), f0, uf(v[3].z) * f1), u4, 4);
        float a3 = tr(fmaf(uf(v[0].w), f0, uf(v[1].w) * f1), fmaf(uf(v[2].w), f0, uf(v[3].w) * f1), u4, 4);
        float o = tr(tr(a0, a2, u2, 2), tr(a1, a3, u2, 2), u1, 1);
        sts_bf16(sb + SM_O + ((2 * warp + (u4 ? 1 : 0)) * 16 + li * 4 + j4) * 2, o);
        bar_arrive<11, 384>();
    }
}

typedef CUresult (*EncodeFn)(CUtensorMap*, CUtensorMapDataType, cuuint32_t, void*, const cuuint64_t*,
                             const cuuint64_t*, const cuuint32_t*, const cuuint32_t*, CUtensorMapInterleave,
                             CUtensorMapSwizzle, CUtensorMapL2promotion, CUtensorMapFloatOOBfill);

void make_map2(EncodeFn fn, CUtensorMap* m, const void* base, int cols, int rows, int box_rows) {
    cuuint64_t dims[2] = {(cuuint64_t)cols, (cuuint64_t)rows};
    cuuint64_t strides[1] = {(cuuint64_t)cols * 2};
    cuuint32_t box[2] = {64, (cuuint32_t)box_rows};
    cuuint32_t es[2] = {1, 1};
    fn(m, CU_TENSOR_MAP_DATA_TYPE_BFLOAT16, 2, const_cast<void*>(base), dims, strides, box, es,
       CU_TENSOR_MAP_INTERLEAVE_NONE, CU_TENSOR_MAP_SWIZZLE_128B, CU_TENSOR_MAP_L2_PROMOTION_L2_128B,
       CU_TENSOR_MAP_FLOAT_OOB_FILL_NONE);
}
void make_map3(EncodeFn fn, CUtensorMap* m, const void* base) {
    cuuint64_t dims[3] = {64, (cuuint64_t)8 * SK, 4};
    cuuint64_t strides[2] = {512, 128};
    cuuint32_t box[3] = {64, 16, 4};
    cuuint32_t es[3] = {1, 1, 1};
    fn(m, CU_TENSOR_MAP_DATA_TYPE_BFLOAT16, 3, const_cast<void*>(base), dims, strides, box, es,
       CU_TENSOR_MAP_INTERLEAVE_NONE, CU_TENSOR_MAP_SWIZZLE_128B, CU_TENSOR_MAP_L2_PROMOTION_L2_128B,
       CU_TENSOR_MAP_FLOAT_OOB_FILL_NONE);
}

}

extern "C" void kernel_launch(void* const* d_in, const int* in_sizes, int n_in, void* d_out, int out_size) {
    (void)in_sizes; (void)n_in; (void)out_size;
    void* fnp = nullptr;
    cudaDriverEntryPointQueryResult qr;
    cudaGetDriverEntryPoint("cuTensorMapEncodeTiled", &fnp, cudaEnableDefault, &qr);
    EncodeFn fn = (EncodeFn)fnp;
    Maps tm;
    make_map2(fn, &tm.wq, d_in[3], 4096, D, 112);
    make_map3(fn, &tm.k, d_in[1]);
    make_map3(fn, &tm.v, d_in[2]);
    make_map2(fn, &tm.w1, d_in[6], FF, D, 56);
    make_map2(fn, &tm.w3, d_in[7], FF, D, 56);
    make_map2(fn, &tm.w2, d_in[8], D, FF, 56);
    make_map2(fn, &tm.wo, d_in[4], D, 4096, 64);
    Params p;
    p.x = (const __nv_bfloat16*)d_in[0];
    cudaGetSymbolAddress((void**)&p.sc, g_scratch);
    p.out = (__nv_bfloat16*)d_out;
    cudaFuncSetAttribute(fused_kernel, cudaFuncAttributeMaxDynamicSharedMemorySize, SM_TOTAL);
    fused_kernel<<<NCTA, NTHREADS, SM_TOTAL, cudaStreamPerThread>>>(p, tm);
}
```

```cpp
#include <cuda_runtime.h>
#include <cuda_bf16.h>
#include <cuda.h>
#include <stdint.h>

constexpr int PER16 = 659;
constexpr int PERW = 669;
constexpr int TOFF = 680;
constexpr int QDELAY = 2000;
constexpr int STG = 256;
constexpr int ADM = 60;

namespace {

constexpr int D = 448, SK = 65536, WIN = 4096, FF = 1792;
constexpr int NCTA = 128;
constexpr int NTHREADS = 704;

constexpr uint32_t SM_WQ = 0;
constexpr uint32_t SM_K = 28672;
constexpr uint32_t SM_W1 = SM_K + 4 * 16384;
constexpr uint32_t SM_W2 = SM_K + 6 * 16384;
constexpr uint32_t SM_WO = SM_K + 7 * 16384;
constexpr uint32_t SM_BAR = SM_K + 12 * 16384;
constexpr uint32_t SM_XN = SM_BAR + 256;
constexpr uint32_t SM_Q = SM_XN + 1024;
constexpr uint32_t SM_X = SM_Q + 4224;
constexpr uint32_t SM_WM = SM_X + 896;
constexpr uint32_t SM_WL = SM_WM + 128;
constexpr uint32_t SM_P = SM_WQ;
constexpr uint32_t SM_O = SM_P + 1056;
constexpr uint32_t SM_H = SM_O + 512;
constexpr uint32_t SM_F = SM_H + 256;
constexpr uint32_t SM_EP = SM_WL + 128;
constexpr uint32_t SM_TOTAL = SM_EP + 16;
static_assert(SM_TOTAL <= 232448, "smem");

constexpr int B_WQ = 0, B_K = 2, B_V = 10, B_W1 = 18, B_W2 = 20, B_WO = 21;
constexpr int N_INIT = 0, N_H = 1, N_MAX = 2, N_Q = 3, N_KA = 4, N_KB = 5, N_SUM = 6, N_O = 7, N_O2 = 8, N_XN = 9,
              N_GF = 10, N_GF2 = 11, N_P = 12;

struct Scratch {
    float q[2][4096];
    float ml[NCTA][16];
    float4 gg[FF];
    float4 acc[D];
    uint32_t epoch;
    uint32_t pad0[31];
    uint32_t accflag;
    uint32_t pad1[31];
    float o[16][16][64][16];
};
__device__ __align__(1024) Scratch g_scratch;

struct Params {
    const __nv_bfloat16* x;
    const char* wq;
    Scratch* sc;
    __nv_bfloat16* out;
};
struct Maps {
    CUtensorMap wq, k, v, w1, w3, w2, wo;
};

constexpr int SPIN_MAX = 2000000;

__device__ __forceinline__ void mbar_init(uint32_t a) {
    asm volatile("mbarrier.init.shared.b64 [%0], 1;" ::"r"(a) : "memory");
}
__device__ __forceinline__ void mbar_expect(uint32_t a, uint32_t b) {
    asm volatile("mbarrier.arrive.expect_tx.shared.b64 _, [%0], %1;" ::"r"(a), "r"(b) : "memory");
}
__device__ __forceinline__ void mbar_wait(uint32_t a) {
    asm volatile("{\n.reg .pred p;\nW: mbarrier.try_wait.parity.shared.b64 p, [%0], 0;\n@!p bra W;\n}" ::"r"(a) : "memory");
}
__device__ __forceinline__ void mbar_spin(uint32_t a) {
    asm volatile("{\n.reg .pred p;\nW: mbarrier.test_wait.parity.shared.b64 p, [%0], 0;\n@!p bra.uni W;\n}" ::"r"(a) : "memory");
}
__device__ __forceinline__ bool mbar_test(uint32_t a) {
    uint32_t ok;
    asm volatile("{ .reg .pred p; mbarrier.test_wait.parity.shared.b64 p, [%1], 0; selp.u32 %0, 1, 0, p; }"
                 : "=r"(ok)
                 : "r"(a)
                 : "memory");
    return ok;
}
__device__ __forceinline__ uint64_t evict_first() {
    uint64_t pol;
    asm("createpolicy.fractional.L2::evict_first.b64 %0, 1.0;" : "=l"(pol));
    return pol;
}
__device__ __forceinline__ void tma2d(uint32_t dst, const CUtensorMap* tm, int c0, int c1, uint32_t mbar) {
    asm volatile(
        "cp.async.bulk.tensor.2d.shared::cluster.global.mbarrier::complete_tx::bytes.L2::cache_hint "
        "[%0], [%1, {%3, %4}], [%2], %5;" ::"r"(dst),
        "l"(tm), "r"(mbar), "r"(c0), "r"(c1), "l"(evict_first())
        : "memory");
}
__device__ __forceinline__ void tma3d(uint32_t dst, const CUtensorMap* tm, int c1, uint32_t mbar) {
    asm volatile(
        "cp.async.bulk.tensor.3d.shared::cluster.global.mbarrier::complete_tx::bytes.L2::cache_hint "
        "[%0], [%1, {%4, %3, %4}], [%2], %5;" ::"r"(dst),
        "l"(tm), "r"(mbar), "r"(c1), "r"(0), "l"(evict_first())
        : "memory");
}
__device__ __forceinline__ void prefetch_map(const CUtensorMap* tm) {
    asm volatile("prefetch.tensormap [%0];" ::"l"(tm) : "memory");
}
__device__ __forceinline__ bool elect() {
    uint32_t p;
    asm volatile("{ .reg .pred P; elect.sync _|P, 0xffffffff; selp.u32 %0, 1, 0, P; }" : "=r"(p));
    return p;
}
template <int ID, int N>
__device__ __forceinline__ void bar_sync() {
    asm volatile("bar.sync %0, %1;" ::"n"(ID), "n"(N) : "memory");
}
template <int ID, int N>
__device__ __forceinline__ void bar_arrive() {
    asm volatile("bar.arrive %0, %1;" ::"n"(ID), "n"(N) : "memory");
}
__device__ __forceinline__ float4 lds128f(uint32_t a) {
    float4 v;
    asm volatile("ld.shared.v4.f32 {%0,%1,%2,%3}, [%4];" : "=f"(v.x), "=f"(v.y), "=f"(v.z), "=f"(v.w) : "r"(a));
    return v;
}
__device__ __forceinline__ uint32_t lds32(uint32_t a) {
    uint32_t v;
    asm volatile("ld.shared.u32 %0, [%1];" : "=r"(v) : "r"(a));
    return v;
}
__device__ __forceinline__ void sts32(uint32_t a, uint32_t v) {
    asm volatile("st.shared.u32 [%0], %1;" ::"r"(a), "r"(v) : "memory");
}
__device__ __forceinline__ void sts64(uint32_t a, uint32_t x, uint32_t y) {
    asm volatile("st.shared.v2.u32 [%0], {%1,%2};" ::"r"(a), "r"(x), "r"(y) : "memory");
}
__device__ __forceinline__ void sts_bf16(uint32_t a, float v) {
    asm volatile("st.shared.b16 [%0], %1;" ::"r"(a), "h"(__bfloat16_as_ushort(__float2bfloat16_rn(v))) : "memory");
}
__device__ __forceinline__ void ldsm4(uint32_t a, uint32_t* r) {
    asm volatile("ldmatrix.sync.aligned.m8n8.x4.shared.b16 {%0,%1,%2,%3}, [%4];"
                 : "=r"(r[0]), "=r"(r[1]), "=r"(r[2]), "=r"(r[3])
                 : "r"(a));
}
__device__ __forceinline__ void ldsm4t(uint32_t a, uint32_t* r) {
    asm volatile("ldmatrix.sync.aligned.m8n8.x4.trans.shared.b16 {%0,%1,%2,%3}, [%4];"
                 : "=r"(r[0]), "=r"(r[1]), "=r"(r[2]), "=r"(r[3])
                 : "r"(a));
}
__device__ __forceinline__ void mma(float* c, const uint32_t* a, uint32_t b0, uint32_t b1) {
    asm volatile(
        "mma.sync.aligned.m16n8k16.row.col.f32.bf16.bf16.f32 {%0,%1,%2,%3}, {%4,%5,%6,%7}, {%8,%9}, {%0,%1,%2,%3};"
        : "+f"(c[0]), "+f"(c[1]), "+f"(c[2]), "+f"(c[3])
        : "r"(a[0]), "r"(a[1]), "r"(a[2]), "r"(a[3]), "r"(b0), "r"(b1));
}
__device__ __forceinline__ void gemv7(uint32_t addr, const uint32_t* bf, float* c0, float* c1) {
#pragma unroll
    for (int s = 0; s < 7; s++) {
        uint32_t a[4];
        ldsm4t(addr + s * 2048, a);
        mma((s & 1) ? c1 : c0, a, bf[2 * s], bf[2 * s + 1]);
    }
}
__device__ __forceinline__ float uf(uint32_t u) { return __uint_as_float(u); }
__device__ __forceinline__ uint32_t fu(float f) { return __float_as_uint(f); }
__device__ __forceinline__ float bflo(uint32_t u) { return uf(u << 16); }
__device__ __forceinline__ float bfhi(uint32_t u) { return uf(u & 0xffff0000u); }
__device__ __forceinline__ float bfr(float v) {
    uint32_t u;
    asm("cvt.rn.bf16x2.f32 %0, %1, %2;" : "=r"(u) : "f"(v), "f"(0.f));
    return uf(u);
}
__device__ __forceinline__ uint32_t pack2(float lo, float hi) {
    uint32_t u;
    asm("cvt.rn.bf16x2.f32 %0, %1, %2;" : "=r"(u) : "f"(hi), "f"(lo));
    return u;
}
__device__ __forceinline__ float fexp(float v) {
    float e;
    asm("ex2.approx.ftz.f32 %0, %1;" : "=f"(e) : "f"(v * 1.4426950408889634f));
    return e;
}
__device__ __forceinline__ float silu(float v) { return __fdividef(v, 1.f + fexp(-v)); }
__device__ __forceinline__ float sel4(const float* c, int j) {
    return (j & 2) ? ((j & 1) ? c[3] : c[2]) : ((j & 1) ? c[1] : c[0]);
}
__device__ __forceinline__ float shx(float v, int m) { return __shfl_xor_sync(0xffffffffu, v, m); }
__device__ __forceinline__ float tr(float a, float b, bool upper, int m) {
    float send = upper ? a : b, keep = upper ? b : a;
    return keep + shx(send, m);
}
template <typename T>
__device__ __forceinline__ void materialize(T*& p) {
    asm volatile("" : "+l"(p));
}
__device__ __forceinline__ uint32_t now16() {
    uint32_t t;
    asm volatile("mov.u32 %0, %globaltimer_lo;" : "=r"(t)::"memory");
    return t * 16;
}
__device__ __forceinline__ void wait_until(uint32_t t) {
    while ((int)(now16() - t) < 0) {}
}
__device__ __forceinline__ void spin_cycles(int n) {
    uint32_t c0, c1;
    asm volatile("mov.u32 %0, %clock;" : "=r"(c0)::"memory");
    do { asm volatile("mov.u32 %0, %clock;" : "=r"(c1)::"memory"); } while ((int)(c1 - c0) < n);
}

__device__ __forceinline__ void put1(float* p, float v, uint32_t tag) {
    asm volatile("st.relaxed.gpu.global.u32 [%0], %1;" ::"l"(p), "r"((fu(v) & ~1u) | tag) : "memory");
}
__device__ __forceinline__ void put2(float* p, float a, float b, uint32_t tag) {
    asm volatile("st.relaxed.gpu.global.v2.u32 [%0], {%1,%2};" ::"l"(p), "r"((fu(a) & ~1u) | tag), "r"((fu(b) & ~1u) | tag)
                 : "memory");
}
__device__ __forceinline__ uint4 ldr128(const void* p) {
    uint4 v;
    asm volatile("ld.relaxed.gpu.global.v4.u32 {%0,%1,%2,%3}, [%4];"
                 : "=r"(v.x), "=r"(v.y), "=r"(v.z), "=r"(v.w)
                 : "l"(p)
                 : "memory");
    return v;
}
__device__ __forceinline__ bool bad4(const uint4& v, uint32_t tag) {
    uint32_t t;
    asm("{ .reg .b32 u, w; lop3.b32 w, %1, %2, %5, 0x7e; lop3.b32 u, %3, %4, %5, 0x7e; lop3.b32 %0, w, u, 1, 0xa8; }"
        : "=r"(t)
        : "r"(v.x), "r"(v.y), "r"(v.z), "r"(v.w), "r"(tag));
    return t;
}
template <int N>
__device__ __forceinline__ void gather(uint4* v, const float* p, int stride, uint32_t tag) {
#pragma unroll
    for (int i = 0; i < N; i++) v[i] = ldr128(p + i * stride);
    int it = 0;
    while (true) {
        bool bad[N], any = false;
#pragma unroll
        for (int i = 0; i < N; i++) { bad[i] = bad4(v[i], tag); any |= bad[i]; }
        if (!__any_sync(0xffffffffu, any)) break;
#pragma unroll
        for (int i = 0; i < N; i++)
            if (bad[i]) v[i] = ldr128(p + i * stride);
        if (++it > SPIN_MAX) __trap();
    }
#pragma unroll
    for (int i = 0; i < N; i++) { v[i].x &= ~1u; v[i].y &= ~1u; v[i].z &= ~1u; v[i].w &= ~1u; }
}
__device__ __noinline__ void sum_partials(const float* blk, uint32_t fac, uint32_t dst, uint32_t tag) {
    const int lane = threadIdx.x & 31;
    uint4 v[8];
    gather<8>(v, blk + (lane & 7) * 16 + (lane >> 3) * 4, 128, tag);
    float a0 = 0.f, a1 = 0.f, a2 = 0.f, a3 = 0.f;
#pragma unroll
    for (int i = 0; i < 8; i++) {
        const float f = uf(lds32(fac + ((lane & 7) + 8 * i) * 4));
        a0 = fmaf(f, uf(v[i].x), a0); a1 = fmaf(f, uf(v[i].y), a1);
        a2 = fmaf(f, uf(v[i].z), a2); a3 = fmaf(f, uf(v[i].w), a3);
    }
    const bool u2 = lane & 2, u1 = lane & 1;
    float o = tr(tr(a0, a2, u2, 2), tr(a1, a3, u2, 2), u1, 1);
    o += shx(o, 4);
    if (!(lane & 4)) sts_bf16(dst + ((lane >> 3) * 4 + (lane & 3)) * 2, o);
}
__device__ __forceinline__ void red4(float4* p, float a, float b) {
    asm volatile("red.relaxed.gpu.global.add.v4.f32 [%0], {%1,%2,%3,%4};" ::"l"(p), "f"(a), "f"(b), "f"(1.f), "f"(0.f)
                 : "memory");
}
template <bool IS_S>
__device__ __forceinline__ bool finish(const float (&c)[4][4], int j4, float4* acc, float xres, __nv_bfloat16* outp) {
    float t = j4 ? (c[0][2] + c[1][2]) + (c[2][2] + c[3][2]) : (c[0][0] + c[1][0]) + (c[2][0] + c[3][0]);
    asm volatile("{ .reg .pred p; setp.ge.s32 p, %1, 2; @p exit; }" : "+f"(t) : "r"(j4));
    float os, ob, oc;
    asm volatile("{ .reg .f32 d; atom.relaxed.gpu.global.add.v4.f32 {%0,%1,%2,d}, [%3], {%4,%5,%6,%7}; }"
                 : "=f"(os), "=f"(ob), "=f"(oc)
                 : "l"(acc), "f"(IS_S ? t : 0.f), "f"(IS_S ? 0.f : t), "f"(1.f), "f"(0.f)
                 : "memory");
    const float res = xres + bfr(bfr(IS_S ? os + t : os) * bfr(silu(bfr(IS_S ? ob : ob + t))));
    asm volatile("{ .reg .pred p; setp.eq.f32 p, %2, 0f41F80000; @p st.global.b16 [%0], %1; }" ::"l"(outp),
                 "h"(__bfloat16_as_ushort(__float2bfloat16_rn(res))), "f"(oc)
                 : "memory");
    return oc == 31.f;
}

__global__ void __launch_bounds__(NTHREADS, 1)
fused_kernel(const __grid_constant__ Params p, const __grid_constant__ Maps tm) {
    extern __shared__ __align__(1024) unsigned char smem[];
    const uint32_t t0 = now16();
    asm volatile("{ .reg .pred p; setp.lt.u32 p, %1, 224; @p prefetch.global.L2 [%0]; }" ::"l"(
                     p.wq + ((blockIdx.x & 1) * 224 + threadIdx.x) * 8192 + (blockIdx.x >> 1) * 128),
                 "r"(threadIdx.x)
                 : "memory");
    const uint32_t sb = (uint32_t)__cvta_generic_to_shared(smem);
    const int b = blockIdx.x, set = b >> 6, idx = b & 63;
    const uint32_t bar = sb + SM_BAR;
    if (threadIdx.x == 0) {
        mbar_init(bar + 8 * B_WQ);
        mbar_expect(bar + 8 * B_WQ, 14336);
        tma2d(sb + SM_WQ, &tm.wq, (b >> 1) * 64, (b & 1) * 224, bar + 8 * B_WQ);
        mbar_init(bar + 8 * (B_WQ + 1));
        mbar_expect(bar + 8 * (B_WQ + 1), 14336);
        tma2d(sb + SM_WQ + 14336, &tm.wq, (b >> 1) * 64, (b & 1) * 224 + 112, bar + 8 * (B_WQ + 1));
        prefetch_map(&tm.k);
    }
    const int lane = threadIdx.x & 31;
    const int wid = __shfl_sync(0xffffffffu, threadIdx.x >> 5, 0);
    const bool has_w = b < 112;
    const int cb = b % 7, rg = b / 7;

    if (wid == 0) {
        const bool el = elect();
        bar_sync<N_INIT, NTHREADS>();
        const int row0 = set * SK + (SK - WIN) + idx * 16;
        uint32_t tnext = t0 + TOFF * 16 + STG * (idx - 32) / 4;
#pragma unroll 1
        for (int n = 0; n < 32; n++) {
            const int j = n >> 1;
            if (n == 24) bar_sync<N_KA, 288>();
            if (el && !(n & 1)) mbar_expect(bar + 8 * (B_K + j), 16384);
            while (true) {
                const uint32_t now = now16();
                if ((int)(now - tnext) >= 0) break;
                if (!(n & 1) && n >= 4 && mbar_test(bar + 8 * (B_K + j - 2)) && (int)(now + ADM * 16 - tnext) < 0)
                    tnext = now + ADM * 16;
            }
            if (el)
                tma3d(sb + SM_K + (n < 24 ? n : n - 24) * 8192, n < 16 ? &tm.k : &tm.v,
                      row0 + ((n >> 2) & 3) * (2 * SK) + (n & 3) * 1024, bar + 8 * (B_K + j));
            tnext += PER16 * 8;
            if (n == 8 && el) {
                prefetch_map(&tm.v); prefetch_map(&tm.w1); prefetch_map(&tm.w3); prefetch_map(&tm.w2); prefetch_map(&tm.wo);
            }
        }
        bar_sync<N_KB, 288>();
        if (has_w) {
#pragma unroll 1
            for (int n = 0; n < 10; n++) {
                const int m = n >> 1, hf = n & 1, c = n - 6;
                const int id = n < 6 ? B_W1 + m : B_WO + c;
                if (el && (n >= 6 || !hf)) mbar_expect(bar + 8 * id, n < 6 ? 14336 : 8192);
                wait_until(tnext);
                if (el)
                    tma2d(sb + (n < 6 ? SM_W1 + m * 16384 + hf * 7168 : SM_WO + c * 8192), &tm.w1 + min(m, 3),
                          n < 4 ? (b >> 2) * 64 : cb * 64,
                          n < 4 ? hf * 224 + (b & 3) * 56 : (n < 6 ? hf * 896 + rg * 56 : c * 1024 + rg * 64), bar + 8 * id);
                tnext += n < 6 ? (n < 4 ? PER16 : PERW) * 49 / 8 : PERW * 7;
            }
        }
        return;
    }

    Scratch* sc = p.sc;
    if (wid == 1) {
        uint32_t ep;
        asm volatile("ld.relaxed.gpu.global.u32 %0, [%1];" : "=r"(ep) : "l"(&sc->epoch) : "memory");
        bar_sync<N_INIT, NTHREADS>();
        const uint32_t tag = (ep + 1) & 1u;
        if (lane == 0) sts32(sb + SM_EP, ep);
        __syncwarp();
        bar_arrive<N_XN, 672>();
        if (has_w) {
            if (lane < 16)
                asm volatile("st.relaxed.gpu.global.v4.f32 [%0], {%1,%1,%2,%1};" ::"l"(&sc->gg[b * 16 + lane]), "f"(0.f),
                             "f"(tag ? 64.f : 0.f)
                             : "memory");
            __syncwarp();
            asm volatile("fence.acq_rel.gpu;" ::: "memory");
        } else if (b == NCTA - 1) {
#pragma unroll 1
            for (int i = lane; i < D; i += 32) sc->acc[i] = make_float4(0.f, 0.f, 0.f, 0.f);
            __syncwarp();
            if (lane == 0) asm volatile("st.release.gpu.global.u32 [%0], %1;" ::"l"(&sc->accflag), "r"(tag) : "memory");
        }
        bar_sync<N_SUM, 288>();
        const int hh = lane & 7, sub = lane >> 3;
        const uint32_t wo4 = ((((hh >> 1) & 1) * 4 + sub) * 4 + (hh >> 2) * 2 + (hh & 1)) * 4;
        float mc = uf(lds32(sb + SM_WM + wo4)), lc = uf(lds32(sb + SM_WL + wo4));
        mc = fmaxf(mc, shx(mc, 8)); mc = fmaxf(mc, shx(mc, 16));
        lc += shx(lc, 8); lc += shx(lc, 16);
        if (lane < 8) put2(&sc->ml[b][hh * 2], mc, lc, tag);
        if (!has_w) return;
        mbar_wait(bar + 8 * (B_V + 2));
        uint32_t um[8], ul[8], uq;
        const float* mp = &sc->ml[(rg >> 3) * 64 + (lane >> 2)][(lane & 3) * 4 + ((rg >> 2) & 1) * 2];
        int it = 0;
        bool bad;
#pragma unroll 1
        do {
            if (++it > SPIN_MAX) __trap();
            asm volatile("ld.relaxed.gpu.global.u32 %0, [%1];" : "=r"(uq) : "l"(&sc->ml[(b & ~3) + (lane & 3)][0]) : "memory");
#pragma unroll
            for (int i = 0; i < 8; i++)
                asm volatile("ld.relaxed.gpu.global.v2.u32 {%0,%1}, [%2];" : "=r"(um[i]), "=r"(ul[i]) : "l"(mp + i * 128) : "memory");
            bad = (uq ^ tag) & 1u;
#pragma unroll
            for (int i = 0; i < 8; i += 2) bad |= bad4(make_uint4(um[i], ul[i], um[i + 1], ul[i + 1]), tag);
        } while (__any_sync(0xffffffffu, bad));
        asm volatile("fence.acquire.gpu;" ::: "memory");
        float M = uf(um[0] & ~1u);
#pragma unroll
        for (int i = 1; i < 8; i++) M = fmaxf(M, uf(um[i] & ~1u));
        M = fmaxf(M, shx(M, 4)); M = fmaxf(M, shx(M, 8)); M = fmaxf(M, shx(M, 16));
        float e[8], L = 0.f;
#pragma unroll
        for (int i = 0; i < 8; i++) {
            e[i] = fexp(uf(um[i] & ~1u) - M);
            L = fmaf(uf(ul[i] & ~1u), e[i], L);
        }
        L += shx(L, 4); L += shx(L, 8); L += shx(L, 16);
        const float rl = __fdividef(1.f, L);
#pragma unroll
        for (int i = 0; i < 8; i++) sts32(sb + SM_F + ((lane & 3) * 64 + (lane >> 2) + 8 * i) * 4, fu(e[i] * rl));
        __syncwarp();
        bar_arrive<N_GF, 416>();
        bar_arrive<N_GF2, 160>();
        return;
    }

    if (wid < 14 && elect()) {
        mbar_init(bar + 8 * (2 * wid - 2));
        mbar_init(bar + 8 * (2 * wid - 1));
    }
    __syncwarp();
    const int li = lane >> 3, l7 = lane & 7, j4 = lane & 3, l4 = lane >> 2;

    if (wid >= 10) {
        const int warp = (wid - 10) & 3;
        const uint32_t aoff = sb + (l7 + (li >> 1) * 8) * 128 + (((2 * warp + (li & 1)) ^ l7) << 4);
        const int col16 = warp * 16 + (j4 & 1) * 8 + l4;
        bar_sync<N_INIT, NTHREADS>();
        bar_sync<N_XN, 672>();
        const uint32_t ep = lds32(sb + SM_EP), tag = (ep + 1) & 1u;

        if (wid < 14) {
            {
                uint32_t bf[28];
#pragma unroll
                for (int i = 0; i < 7; i++) ldsm4(sb + SM_XN + (b & 1) * 448 + i * 64 + li * 16, bf + 4 * i);
                float c0[4] = {}, c1[4] = {};
                mbar_wait(bar + 8 * B_WQ);
                gemv7(aoff + SM_WQ, bf, c0, c1);
                mbar_wait(bar + 8 * (B_WQ + 1));
                gemv7(aoff + SM_WQ + 14336, bf + 14, c0, c1);
                if (j4 < 2) put1(&sc->q[b & 1][(b >> 1) * 64 + col16], j4 ? c0[2] + c1[2] : c0[0] + c1[0], tag);
                bar_arrive<N_Q, 384>();
            }
            if (!has_w) return;
            bar_sync<N_GF, 416>();
            uint32_t bf[16];
#pragma unroll
            for (int i = 0; i < 4; i++)
                ldsm4(sb + SM_XN + (b & 3) * 112 + (4 * i + li) * 16 + (4 * i + li >= 7 ? 336 : 0), bf + 4 * i);
            float4* gout = &sc->gg[(b >> 2) * 64 + col16];
            materialize(gout);
            float c0[4] = {}, c1[4] = {}, d0[4] = {}, d1[4] = {};
            mbar_wait(bar + 8 * B_W1);
            gemv7(aoff + SM_W1, bf, c0, c1);
            mbar_wait(bar + 8 * (B_W1 + 1));
            gemv7(aoff + SM_W1 + 16384, bf, d0, d1);
            if (j4 < 2) red4(gout, j4 ? c0[2] + c1[2] : c0[0] + c1[0], j4 ? d0[2] + d1[2] : d0[0] + d1[0]);
            return;
        }

        if (!has_w) return;
        const int ocol = cb * 64 + col16;
        float4* accp = &sc->acc[ocol];
        __nv_bfloat16* outp = p.out + ocol;
        const uint32_t xu = lds32(sb + SM_X + (ocol >> 1) * 4);
        const float xres = (ocol & 1) ? bfhi(xu) : bflo(xu);
        materialize(accp);
        materialize(outp);
        if (wid == 14) {
            mbar_wait(bar + 8 * (B_K + 6));
            for (int it = 0;; it++) {
                uint32_t v;
                asm volatile("ld.acquire.gpu.global.u32 %0, [%1];" : "=r"(v) : "l"(&sc->accflag) : "memory");
                if (v == tag) break;
                if (it > SPIN_MAX) __trap();
            }
        }
        bar_sync<N_GF, 416>();
#pragma unroll 1
        for (int q = wid >= 18; q < 3; q += 2) {
            mbar_wait(bar + 8 * (B_V + (q == 2 ? 7 : 4 + q)));
            sum_partials(&sc->o[4 * q + (rg >> 2)][(rg & 3) * 4 + warp][0][0], sb + SM_F + q * 256,
                         sb + SM_O + (q * 64 + warp * 16) * 2, tag);
        }
        float c[4][4] = {};
        bool last;
        if (wid >= 18) {
            bar_arrive<N_O, 256>();
            const int tid = warp * 32 + lane;
            const float4* gp = &sc->gg[rg * 56 + min(tid, 111) + (tid >= 56 ? 840 : 0)];
            const uint32_t want = fu(tag ? 68.f : 4.f);
            uint32_t a[7][4], bf[16];
            mbar_wait(bar + 8 * B_W2);
            uint4 v = ldr128(gp);
#pragma unroll
            for (int s = 0; s < 7; s++) ldsm4t(aoff + SM_W2 + s * 2048, a[s]);
            for (int it = 0;; it++) {
                const bool bad = v.z != want;
                if (!__any_sync(0xffffffffu, bad)) break;
                if (bad) v = ldr128(gp);
                if (it > SPIN_MAX) __trap();
            }
            sts_bf16(sb + SM_H + tid * 2, bfr(silu(bfr(uf(v.x)))) * bfr(uf(v.y)));
            bar_sync<N_H, 128>();
#pragma unroll
            for (int i = 0; i < 4; i++) ldsm4(sb + SM_H + i * 64 + li * 16, bf + 4 * i);
#pragma unroll
            for (int s = 0; s < 7; s++) mma(c[s & 3], a[s], bf[2 * s], bf[2 * s + 1]);
            last = finish<false>(c, j4, accp, xres, outp);
        } else {
            uint32_t bf[32];
            bar_sync<N_O, 256>();
#pragma unroll
            for (int i = 0; i < 6; i++) ldsm4(sb + SM_O + i * 64 + li * 16, bf + 4 * i);
#pragma unroll
            for (int h = 0; h < 4; h++) {
                if (h == 2) {
                    bar_sync<N_O2, 256>();
                    ldsm4(sb + SM_O + 384 + li * 16, bf + 24);
                    ldsm4(sb + SM_O + 448 + li * 16, bf + 28);
                }
                uint32_t a[4][4];
                mbar_spin(bar + 8 * (B_WO + h));
#pragma unroll
                for (int s = 0; s < 4; s++) ldsm4t(aoff + SM_WO + (4 * h + s) * 2048, a[s]);
#pragma unroll
                for (int s = 0; s < 4; s++) mma(c[s], a[s], bf[8 * h + 2 * s], bf[8 * h + 2 * s + 1]);
            }
            last = finish<true>(c, j4, accp, xres, outp);
        }
        if (last && ocol == 0) sc->epoch = ep + 1;
        return;
    }

    const int warp = wid - 2, tid = threadIdx.x - 64;
    if (warp == 7) {
        uint4 xa = make_uint4(0, 0, 0, 0), xb = xa;
        if (lane < 28) {
            xa = __ldg(reinterpret_cast<const uint4*>(p.x) + lane);
            xb = __ldg(reinterpret_cast<const uint4*>(p.x) + 28 + lane);
        }
        bar_sync<N_INIT, NTHREADS>();
        if (lane < 28) {
            sts64(sb + SM_X + lane * 16, xa.x, xa.y); sts64(sb + SM_X + lane * 16 + 8, xa.z, xa.w);
            sts64(sb + SM_X + 448 + lane * 16, xb.x, xb.y); sts64(sb + SM_X + 456 + lane * 16, xb.z, xb.w);
        }
        __syncwarp();
        uint32_t xv[7];
        float s = 0.f;
#pragma unroll
        for (int i = 0; i < 7; i++) {
            xv[i] = lds32(sb + SM_X + (lane + 32 * i) * 4);
            s += bflo(xv[i]) + bfhi(xv[i]);
        }
#pragma unroll
        for (int m = 16; m; m >>= 1) s += shx(s, m);
        const float mean = s * (1.f / D);
        float vs = 0.f;
#pragma unroll
        for (int i = 0; i < 7; i++) {
            const float a = bflo(xv[i]) - mean, c = bfhi(xv[i]) - mean;
            vs += a * a + c * c;
        }
#pragma unroll
        for (int m = 16; m; m >>= 1) vs += shx(vs, m);
        const float mb = bfr(mean);
        const float sd = bfr(sqrtf(bfr(bfr(vs * (1.f / D)) + 1e-5f)));
#pragma unroll 1
        for (int i = lane * 4; i < 896; i += 128) {
            const uint32_t u = lds32(sb + SM_X + i);
            sts32(sb + SM_XN + i, pack2(bfr(bflo(u) - mb) / sd, bfr(bfhi(u) - mb) / sd));
        }
    } else {
        bar_sync<N_INIT, NTHREADS>();
    }
    bar_sync<N_XN, 672>();
    const uint32_t tag = (lds32(sb + SM_EP) + 1) & 1u;

    float* op = &sc->o[2 * set + (j4 & 1)][2 * warp][idx][(j4 >> 1) * 8 + l4];

    {
        mbar_wait(bar + 8 * (B_WQ + 1));
        spin_cycles(QDELAY);
        uint4 v[4];
        gather<4>(v, &sc->q[0][(2 * (tid >> 7) + set) * 512 + (tid & 127) * 4], 2048, tag);
        const uint32_t qa = sb + SM_Q + (tid >> 6) * 528 + (tid & 63) * 8;
#pragma unroll
        for (int i = 0; i < 2; i++)
            sts64(qa + i * 2112, pack2(uf(v[i].x) + uf(v[i + 2].x), uf(v[i].y) + uf(v[i + 2].y)),
                  pack2(uf(v[i].z) + uf(v[i + 2].z), uf(v[i].w) + uf(v[i + 2].w)));
    }
    bar_sync<N_Q, 384>();

    {
        float s0 = 0.f, s1 = 0.f;
        const uint32_t krow = sb + SM_K + warp * 8192 + (l7 + (li & 1) * 8) * 128;
#pragma unroll 1
        for (int h = 0; h < 2; h++) {
            uint32_t bf[32];
#pragma unroll
            for (int i = 0; i < 8; i++)
                ldsm4(sb + SM_Q + (2 * h + (warp >> 2)) * 1056 + (lane & 1) * 528 + i * 64 + li * 16, bf + 4 * i);
            float c0[4] = {}, c1[4] = {};
            mbar_wait(bar + 8 * (B_K + h * 4 + (warp >> 1)));
#pragma unroll
            for (int ks = 0; ks < 16; ks++) {
                uint32_t a[4];
                ldsm4(krow + h * 65536 + (ks >> 2) * 2048 + ((((ks & 3) * 2 + (li >> 1)) ^ l7) << 4), a);
                mma((ks & 1) ? c1 : c0, a, bf[2 * ks], bf[2 * ks + 1]);
            }
            s0 = s1;
            s1 = bfr(sel4(c0, j4) + sel4(c1, j4)) * 0.0625f;
            if (h == 0) {
                bar_arrive<N_KA, 288>();
                put1(op + 12 * 16384, 0.f, tag ^ 1u);
                put1(op + 12 * 16384 + 1024, 0.f, tag ^ 1u);
            }
        }
        float m0 = s0, m1 = s1;
#pragma unroll
        for (int m = 2; m < 32; m <<= 1) { m0 = fmaxf(m0, shx(m0, m)); m1 = fmaxf(m1, shx(m1, m)); }
        if (lane < 4) sts32(sb + SM_WM + (warp * 4 + lane) * 4, fu((lane & 2) ? m1 : m0));
        bar_sync<N_MAX, 256>();
#pragma unroll
        for (int i = 0; i < 4; i++) {
            const float4 w = lds128f(sb + SM_WM + ((warp & 4) + i) * 16);
            m0 = fmaxf(m0, (j4 & 1) ? w.y : w.x);
            m1 = fmaxf(m1, (j4 & 1) ? w.w : w.z);
        }
        float e0 = fexp(s0 - m0), e1 = fexp(s1 - m1);
        const uint32_t pa = sb + SM_P + (j4 & 1) * 528 + (warp * 16 + (j4 >> 1) * 8 + l4) * 2;
        sts_bf16(pa, e0);
        sts_bf16(pa + 256, e1);
#pragma unroll
        for (int m = 2; m < 32; m <<= 1) { e0 += shx(e0, m); e1 += shx(e1, m); }
        if (lane < 4) sts32(sb + SM_WL + (warp * 4 + lane) * 4, fu((lane & 2) ? e1 : e0));
        bar_arrive<N_SUM, 288>();
        bar_sync<N_P, 256>();
    }

    {
        float c0[4] = {}, c1[4] = {};
        const uint32_t vrow = sb + SM_K + (warp >> 1) * 2048 + (l7 + (li >> 1) * 8) * 128;
        const uint32_t ch0 = (((warp & 1) * 4 + (li & 1)) ^ l7) << 4, ch1 = ch0 ^ 32;
#pragma unroll 1
        for (int c = 0; c < 8; c++) {
            uint32_t pf[4];
            ldsm4(sb + SM_P + (lane & 1) * 528 + c * 64 + li * 16, pf);
            mbar_wait(bar + 8 * (B_V + c));
            const uint32_t base = vrow + (c < 4 ? c + 8 : c - 4) * 16384;
#pragma unroll
            for (int u = 0; u < 2; u++) {
                uint32_t a0[4], a1[4];
                ldsm4t(base + u * 8192 + ch0, a0);
                ldsm4t(base + u * 8192 + ch1, a1);
                mma(c0, a0, pf[2 * u], pf[2 * u + 1]);
                mma(c1, a1, pf[2 * u], pf[2 * u + 1]);
            }
            if (c == 0) bar_arrive<N_KB, 288>();
            if (c & 1) {
                put1(op, sel4(c0, j4), tag);
                put1(op + 1024, sel4(c1, j4), tag);
                op += 4 * 16384;
#pragma unroll
                for (int i = 0; i < 4; i++) c0[i] = c1[i] = 0.f;
            }
        }
    }
    if (has_w && warp < 4) {
        bar_sync<N_GF2, 160>();
        mbar_wait(bar + 8 * B_W1);
        sum_partials(&sc->o[12 + (rg >> 2)][(rg & 3) * 4 + warp][0][0], sb + SM_F + 768,
                     sb + SM_O + (192 + warp * 16) * 2, tag);
        bar_arrive<N_O2, 256>();
    }
}

typedef CUresult (*EncodeFn)(CUtensorMap*, CUtensorMapDataType, cuuint32_t, void*, const cuuint64_t*,
                             const cuuint64_t*, const cuuint32_t*, const cuuint32_t*, CUtensorMapInterleave,
                             CUtensorMapSwizzle, CUtensorMapL2promotion, CUtensorMapFloatOOBfill);

void make_map2(EncodeFn fn, CUtensorMap* m, const void* base, int cols, int rows, int box_rows) {
    cuuint64_t dims[2] = {(cuuint64_t)cols, (cuuint64_t)rows};
    cuuint64_t strides[1] = {(cuuint64_t)cols * 2};
    cuuint32_t box[2] = {64, (cuuint32_t)box_rows};
    cuuint32_t es[2] = {1, 1};
    fn(m, CU_TENSOR_MAP_DATA_TYPE_BFLOAT16, 2, const_cast<void*>(base), dims, strides, box, es,
       CU_TENSOR_MAP_INTERLEAVE_NONE, CU_TENSOR_MAP_SWIZZLE_128B, CU_TENSOR_MAP_L2_PROMOTION_L2_128B,
       CU_TENSOR_MAP_FLOAT_OOB_FILL_NONE);
}
void make_map3(EncodeFn fn, CUtensorMap* m, const void* base) {
    cuuint64_t dims[3] = {64, (cuuint64_t)8 * SK, 4};
    cuuint64_t strides[2] = {512, 128};
    cuuint32_t box[3] = {64, 16, 4};
    cuuint32_t es[3] = {1, 1, 1};
    fn(m, CU_TENSOR_MAP_DATA_TYPE_BFLOAT16, 3, const_cast<void*>(base), dims, strides, box, es,
       CU_TENSOR_MAP_INTERLEAVE_NONE, CU_TENSOR_MAP_SWIZZLE_128B, CU_TENSOR_MAP_L2_PROMOTION_L2_128B,
       CU_TENSOR_MAP_FLOAT_OOB_FILL_NONE);
}

}

extern "C" void kernel_launch(void* const* d_in, const int* in_sizes, int n_in, void* d_out, int out_size) {
    (void)in_sizes; (void)n_in; (void)out_size;
    void* fnp = nullptr;
    cudaDriverEntryPointQueryResult qr;
    cudaGetDriverEntryPoint("cuTensorMapEncodeTiled", &fnp, cudaEnableDefault, &qr);
    EncodeFn fn = (EncodeFn)fnp;
    Maps tm;
    make_map2(fn, &tm.wq, d_in[3], 4096, D, 112);
    make_map3(fn, &tm.k, d_in[1]);
    make_map3(fn, &tm.v, d_in[2]);
    make_map2(fn, &tm.w1, d_in[6], FF, D, 56);
    make_map2(fn, &tm.w3, d_in[7], FF, D, 56);
    make_map2(fn, &tm.w2, d_in[8], D, FF, 56);
    make_map2(fn, &tm.wo, d_in[4], D, 4096, 64);
    Params p;
    p.x = (const __nv_bfloat16*)d_in[0];
    p.wq = (const char*)d_in[3];
    cudaGetSymbolAddress((void**)&p.sc, g_scratch);
    p.out = (__nv_bfloat16*)d_out;
    cudaFuncSetAttribute(fused_kernel, cudaFuncAttributeMaxDynamicSharedMemorySize, SM_TOTAL);
    fused_kernel<<<NCTA, NTHREADS, SM_TOTAL, cudaStreamPerThread>>>(p, tm);
}
```
